```python
import torch

def _softmax(x, axis=-1):
    return torch.softmax(x, dim=axis)
def _gelu(x):
    return torch.nn.functional.gelu(x, approximate="tanh")
def _silu(x):
    return torch.nn.functional.silu(x)
def _sigmoid(x):
    return torch.sigmoid(x)
def _layernorm(x, axis=-1, eps=1e-5):
    m = x.mean(dim=axis, keepdim=True)
    v = x.var(dim=axis, keepdim=True, unbiased=False)
    return (x - m) / torch.sqrt(v + eps)
def _scatter_add(tgt, idx, src, axis=0):
    return tgt.clone().index_add_(axis, idx, src)
def _segment_sum(src, seg, n):
    out = torch.zeros((n,) + src.shape[1:], dtype=src.dtype)
    return out.index_add_(0, seg, src)
def _pad(x, pw):
    flat = tuple(v for pair in reversed(pw) for v in pair)
    return torch.nn.functional.pad(x, flat)

kernel_name = 'recurrent_scan__mha_block__swiglu_ffn__prompt'

def setup_inputs():

    _w = (lambda a: (lambda t: t.to(torch.bfloat16) if t.is_floating_point() else t)(torch.as_tensor(a)))
    def _A_setup():
        B, S, D, H = 1, 2048, 576, 32
        return {
            "x": _w((lambda *s: torch.randn(*s, dtype=torch.bfloat16) * 0.05)(B, S, D)),
            "wqkv": _w((lambda *s: torch.randn(*s, dtype=torch.bfloat16) * 0.05)(D, 3 * D)),
            "wo": _w((lambda *s: torch.randn(*s, dtype=torch.bfloat16) * 0.05)(D, D)),
        }
    _A_in = _A_setup()

    def _B_setup():
        B, S, D, F = 1, 2048, 576, 4608
        return {
            "x": _w((lambda *s: torch.randn(*s, dtype=torch.bfloat16) * 0.05)(B, S, D)),
            "w_gate": _w((lambda *s: torch.randn(*s, dtype=torch.bfloat16) * 0.05)(D, F)),
            "w_up": _w((lambda *s: torch.randn(*s, dtype=torch.bfloat16) * 0.05)(D, F)),
            "w_down": _w((lambda *s: torch.randn(*s, dtype=torch.bfloat16) * 0.05)(F, D)),
        }
    _B_in = _B_setup()

    return {
        "A_x": _A_in["x"],
        "A_wqkv": _A_in["wqkv"],
        "A_wo": _A_in["wo"],
        "B_x": _B_in["x"],
        "B_w_gate": _B_in["w_gate"],
        "B_w_up": _B_in["w_up"],
        "B_w_down": _B_in["w_down"],
    }

def reference(A_x, A_wqkv, A_wo, B_x, B_w_gate, B_w_up, B_w_down):
    def _A_ref(x, wqkv, wo):
        B, S, D = x.shape
        H = 32
        Dh = D // H
        qkv = (lambda x, *d: x.permute(*d))((x @ wqkv).reshape(B, S, 3, H, Dh), 2, 0, 3, 1, 4)
        q, k, v = qkv[0], qkv[1], qkv[2]
        scores = torch.einsum("bhqd,bhkd->bhqk", q, k) * (Dh ** -0.5)
        p = _softmax(scores, axis=-1)
        o = torch.einsum("bhqk,bhkd->bhqd", p, v)
        return (lambda x, *d: x.permute(*d))(o, 0, 2, 1, 3).reshape(B, S, D) @ wo

    def _B_ref(x, w_gate, w_up, w_down):
        g = _silu(x @ w_gate)
        u = x @ w_up
        return (g * u) @ w_down

    x = A_x
    xn = _layernorm(x, axis=-1)
    s = _A_ref(xn, A_wqkv, A_wo)
    g = _silu(_B_ref(xn, B_w_gate, B_w_up, B_w_down))
    return x + s * g
```

```cpp
#include <cuda_runtime.h>
#include <cuda_bf16.h>
#include <cuda_fp16.h>
#include <cuda.h>
#include <stdint.h>

namespace {

typedef __nv_bfloat16 bf16;

constexpr int SEQ = 2048, DM = 576, FF = 4608, NH = 32, DH = 18;

__device__ __align__(1024) bf16 g_QKV[3 * NH * 3 * SEQ * 8];
__device__ __align__(1024) bf16 g_H[SEQ * FF];
__device__ __align__(1024) bf16 g_O[SEQ * DM];
__device__ __align__(1024) float g_part[32 * 4 * 4 * 36 * 256];
__device__ unsigned int g_cnt[32];
__device__ unsigned int g_cnt_qkv;
__device__ unsigned int g_cnt_h[64];
__device__ unsigned int g_epoch;
__device__ unsigned int g_done;

#define TS(kern, wgi, slot) do { } while (0)
__device__ __forceinline__ uint32_t smem_u32(const void* p) { return (uint32_t)__cvta_generic_to_shared(p); }
__device__ __forceinline__ uint32_t cluster_rank() { uint32_t r; asm volatile("mov.u32 %0, %%cluster_ctarank;" : "=r"(r)); return r; }
__device__ __forceinline__ void cluster_sync_all() {
    asm volatile("barrier.cluster.arrive.relaxed.aligned;\nbarrier.cluster.wait.aligned;" ::: "memory");
}
__device__ __forceinline__ void mbar_init(uint32_t bar, uint32_t cnt) {
    asm volatile("mbarrier.init.shared::cta.b64 [%0], %1;" :: "r"(bar), "r"(cnt) : "memory");
}
__device__ __forceinline__ void mbar_expect_tx(uint32_t bar, uint32_t bytes) {
    asm volatile("mbarrier.arrive.expect_tx.shared::cta.b64 _, [%0], %1;" :: "r"(bar), "r"(bytes) : "memory");
}
__device__ __forceinline__ void mbar_arrive(uint32_t bar) {
    asm volatile("mbarrier.arrive.shared::cta.b64 _, [%0];" :: "r"(bar) : "memory");
}
__device__ __forceinline__ void mbar_arrive_remote(uint32_t bar, uint32_t cta) {
    asm volatile("{\n.reg .b32 ra;\nmapa.shared::cluster.u32 ra, %0, %1;\n"
                 "mbarrier.arrive.shared::cluster.b64 _, [ra];\n}" :: "r"(bar), "r"(cta) : "memory");
}
__device__ __forceinline__ bool mbar_try_wait(uint32_t bar, uint32_t parity) {
    uint32_t ok;
    asm volatile("{\n.reg .pred p;\nmbarrier.try_wait.parity.shared::cta.b64 p, [%1], %2;\nselp.u32 %0, 1, 0, p;\n}"
                 : "=r"(ok) : "r"(bar), "r"(parity) : "memory");
    return ok != 0;
}
__device__ __forceinline__ void mbar_wait(uint32_t bar, uint32_t parity) {
    if (mbar_try_wait(bar, parity)) return;
#pragma unroll 1
    for (uint32_t n = 0; n < (1u << 24); n++) { if (mbar_try_wait(bar, parity)) break; }
}
__device__ __forceinline__ void wait_counter(const unsigned int* p, unsigned int target) {
#pragma unroll 1
    for (uint32_t n = 0; n < (1u << 22); n++) {
        uint32_t v;
        asm volatile("ld.acquire.gpu.global.u32 %0, [%1];" : "=r"(v) : "l"(p) : "memory");
        if ((int)(v - target) >= 0) break;
        __nanosleep(32);
    }
}
__device__ __forceinline__ void signal_counter(unsigned int* p) {
    asm volatile("fence.proxy.async;" ::: "memory");
    __threadfence();
    atomicAdd(p, 1u);
}
__device__ __forceinline__ unsigned int read_epoch() {
    uint32_t v; asm volatile("ld.relaxed.gpu.global.u32 %0, [%1];" : "=r"(v) : "l"(&g_epoch) : "memory"); return v;
}
__device__ __forceinline__ void pdl_wait() { asm volatile("griddepcontrol.wait;" ::: "memory"); }
__device__ __forceinline__ void pdl_launch() { asm volatile("griddepcontrol.launch_dependents;" ::: "memory"); }
__device__ __forceinline__ void fence_barrier_init() { asm volatile("fence.mbarrier_init.release.cluster;" ::: "memory"); }
__device__ __forceinline__ void fence_proxy_async() { asm volatile("fence.proxy.async.shared::cta;" ::: "memory"); }
__device__ __forceinline__ void tma_2d(uint32_t dst, const CUtensorMap* tm, int c0, int c1, uint32_t bar) {
    asm volatile("cp.async.bulk.tensor.2d.shared::cluster.global.mbarrier::complete_tx::bytes [%0], [%1, {%3, %4}], [%2];"
                 :: "r"(dst), "l"(tm), "r"(bar), "r"(c0), "r"(c1) : "memory");
}
__device__ __forceinline__ void tma_2d_mc(uint32_t dst, const CUtensorMap* tm, int c0, int c1, uint32_t bar, uint16_t mask) {
    asm volatile("cp.async.bulk.tensor.2d.shared::cluster.global.mbarrier::complete_tx::bytes.multicast::cluster [%0], [%1, {%3, %4}], [%2], %5;"
                 :: "r"(dst), "l"(tm), "r"(bar), "r"(c0), "r"(c1), "h"(mask) : "memory");
}
__device__ __forceinline__ void tma_5d_mc(uint32_t dst, const CUtensorMap* tm, int c0, int c4, uint32_t bar, uint16_t mask) {
    asm volatile("cp.async.bulk.tensor.5d.shared::cluster.global.mbarrier::complete_tx::bytes.multicast::cluster [%0], [%1, {%3, %5, %5, %5, %4}], [%2], %6;"
                 :: "r"(dst), "l"(tm), "r"(bar), "r"(c0), "r"(c4), "r"(0), "h"(mask) : "memory");
}
__device__ __forceinline__ void bulk_g2s(uint32_t dst, const void* src, uint32_t bytes, uint32_t bar) {
    asm volatile("cp.async.bulk.shared::cluster.global.mbarrier::complete_tx::bytes [%0], [%1], %2, [%3];"
                 :: "r"(dst), "l"(src), "r"(bytes), "r"(bar) : "memory");
}
__device__ __forceinline__ void prefetch_l2(const void* p, uint32_t bytes) {
    asm volatile("cp.async.bulk.prefetch.L2.global [%0], %1;" :: "l"(p), "r"(bytes) : "memory");
}
__device__ __forceinline__ void prefetch_tmap(const CUtensorMap* tm) {
    asm volatile("prefetch.tensormap [%0];" :: "l"(tm) : "memory");
}
__device__ __forceinline__ void bar_sync(int id, int n) { asm volatile("bar.sync %0, %1;" :: "r"(id), "r"(n) : "memory"); }
__device__ __forceinline__ void bar_arrive(int id, int n) { asm volatile("bar.arrive %0, %1;" :: "r"(id), "r"(n) : "memory"); }
#define WG_FENCE() asm volatile("wgmma.fence.sync.aligned;" ::: "memory")
#define WG_COMMIT() asm volatile("wgmma.commit_group.sync.aligned;" ::: "memory")
#define WG_WAIT(n) asm volatile("wgmma.wait_group.sync.aligned %0;" :: "n"(n) : "memory")
template <int N> __device__ __forceinline__ void fence_regs(float (&a)[N]) {
#pragma unroll
    for (int i = 0; i < N; i++) asm volatile("" : "+f"(a[i]) :: "memory");
}
__device__ __forceinline__ uint32_t desc_lo(uint32_t addr, uint32_t lbo) { return ((addr & 0x3FFFF) >> 4) | ((lbo >> 4) << 16); }
constexpr uint32_t desc_hi(uint32_t sbo, uint32_t swz) { return (sbo >> 4) | (swz << 30); }
constexpr uint32_t HI_SW128 = desc_hi(1024, 1), HI_SW64 = desc_hi(512, 2), HI_K = desc_hi(128, 0), HI_V = desc_hi(32768, 0);
__device__ __forceinline__ float ex2(float x) { float y; asm("ex2.approx.ftz.f32 %0, %1;" : "=f"(y) : "f"(x)); return y; }
__device__ __forceinline__ float sqrt_approx(float x) { float y; asm("sqrt.approx.f32 %0, %1;" : "=f"(y) : "f"(x)); return y; }
__device__ __forceinline__ float bf16r(float x) { return __bfloat162float(__float2bfloat16_rn(x)); }
__device__ __forceinline__ uint32_t pack_bf16(float lo, float hi) {
    uint32_t r; asm("cvt.rn.bf16x2.f32 %0, %1, %2;" : "=r"(r) : "f"(hi), "f"(lo)); return r;
}
__device__ __forceinline__ float bf_lo(uint32_t v) { return __uint_as_float(v << 16); }
__device__ __forceinline__ float bf_hi(uint32_t v) { return __uint_as_float(v & 0xFFFF0000u); }
__device__ __forceinline__ float silu_f(float g) { return __fdividef(g, 1.0f + ex2(-1.4426950408889634f * g)); }

template <uint32_t BHI>
__device__ __forceinline__ void wgmma_rs_n24_tb1(float (&d)[12], uint32_t a0, uint32_t a1, uint32_t a2, uint32_t a3, uint32_t blo, int scale_d) {
    asm volatile("{\n.reg .pred p;\n.reg .b64 db;\nsetp.ne.b32 p, %17, 0;\nmov.b64 db, {%16, %18};\n"
        "wgmma.mma_async.sync.aligned.m64n24k16.f32.bf16.bf16 {%0, %1, %2, %3, %4, %5, %6, %7, %8, %9, %10, %11}, {%12, %13, %14, %15}, db, p, 1, 1, 1;\n}\n"
        : "+f"(d[0]), "+f"(d[1]), "+f"(d[2]), "+f"(d[3]), "+f"(d[4]), "+f"(d[5]), "+f"(d[6]), "+f"(d[7]), "+f"(d[8]), "+f"(d[9]), "+f"(d[10]), "+f"(d[11])
        : "r"(a0), "r"(a1), "r"(a2), "r"(a3), "r"(blo), "r"(scale_d), "n"(BHI));
}

template <uint32_t BHI>
__device__ __forceinline__ void wgmma_rs_n64_tb0(float (&d)[32], uint32_t a0, uint32_t a1, uint32_t a2, uint32_t a3, uint32_t blo, int scale_d) {
    asm volatile("{\n.reg .pred p;\n.reg .b64 db;\nsetp.ne.b32 p, %37, 0;\nmov.b64 db, {%36, %38};\n"
        "wgmma.mma_async.sync.aligned.m64n64k16.f32.bf16.bf16 {%0, %1, %2, %3, %4, %5, %6, %7, %8, %9, %10, %11, %12, %13, %14, %15, %16, %17, %18, %19, %20, %21, %22, %23, %24, %25, %26, %27, %28, %29, %30, %31}, {%32, %33, %34, %35}, db, p, 1, 1, 0;\n}\n"
        : "+f"(d[0]), "+f"(d[1]), "+f"(d[2]), "+f"(d[3]), "+f"(d[4]), "+f"(d[5]), "+f"(d[6]), "+f"(d[7]), "+f"(d[8]), "+f"(d[9]), "+f"(d[10]), "+f"(d[11]), "+f"(d[12]), "+f"(d[13]), "+f"(d[14]), "+f"(d[15]), "+f"(d[16]), "+f"(d[17]), "+f"(d[18]), "+f"(d[19]), "+f"(d[20]), "+f"(d[21]), "+f"(d[22]), "+f"(d[23]), "+f"(d[24]), "+f"(d[25]), "+f"(d[26]), "+f"(d[27]), "+f"(d[28]), "+f"(d[29]), "+f"(d[30]), "+f"(d[31])
        : "r"(a0), "r"(a1), "r"(a2), "r"(a3), "r"(blo), "r"(scale_d), "n"(BHI));
}

template <uint32_t AHI, uint32_t BHI>
__device__ __forceinline__ void wgmma_ss_n112_tb1(float (&d)[56], uint32_t alo, uint32_t blo, int scale_d) {
    asm volatile("{\n.reg .pred p;\n.reg .b64 da, db;\nsetp.ne.b32 p, %58, 0;\nmov.b64 da, {%56, %59};\nmov.b64 db, {%57, %60};\n"
        "wgmma.mma_async.sync.aligned.m64n112k16.f32.bf16.bf16 {%0, %1, %2, %3, %4, %5, %6, %7, %8, %9, %10, %11, %12, %13, %14, %15, %16, %17, %18, %19, %20, %21, %22, %23, %24, %25, %26, %27, %28, %29, %30, %31, %32, %33, %34, %35, %36, %37, %38, %39, %40, %41, %42, %43, %44, %45, %46, %47, %48, %49, %50, %51, %52, %53, %54, %55}, da, db, p, 1, 1, 0, 1;\n}\n"
        : "+f"(d[0]), "+f"(d[1]), "+f"(d[2]), "+f"(d[3]), "+f"(d[4]), "+f"(d[5]), "+f"(d[6]), "+f"(d[7]), "+f"(d[8]), "+f"(d[9]), "+f"(d[10]), "+f"(d[11]), "+f"(d[12]), "+f"(d[13]), "+f"(d[14]), "+f"(d[15]), "+f"(d[16]), "+f"(d[17]), "+f"(d[18]), "+f"(d[19]), "+f"(d[20]), "+f"(d[21]), "+f"(d[22]), "+f"(d[23]), "+f"(d[24]), "+f"(d[25]), "+f"(d[26]), "+f"(d[27]), "+f"(d[28]), "+f"(d[29]), "+f"(d[30]), "+f"(d[31]), "+f"(d[32]), "+f"(d[33]), "+f"(d[34]), "+f"(d[35]), "+f"(d[36]), "+f"(d[37]), "+f"(d[38]), "+f"(d[39]), "+f"(d[40]), "+f"(d[41]), "+f"(d[42]), "+f"(d[43]), "+f"(d[44]), "+f"(d[45]), "+f"(d[46]), "+f"(d[47]), "+f"(d[48]), "+f"(d[49]), "+f"(d[50]), "+f"(d[51]), "+f"(d[52]), "+f"(d[53]), "+f"(d[54]), "+f"(d[55])
        : "r"(alo), "r"(blo), "r"(scale_d), "n"(AHI), "n"(BHI));
}

template <uint32_t AHI, uint32_t BHI>
__device__ __forceinline__ void wgmma_ss_n128_tb1(float (&d)[64], uint32_t alo, uint32_t blo, int scale_d) {
    asm volatile("{\n.reg .pred p;\n.reg .b64 da, db;\nsetp.ne.b32 p, %66, 0;\nmov.b64 da, {%64, %67};\nmov.b64 db, {%65, %68};\n"
        "wgmma.mma_async.sync.aligned.m64n128k16.f32.bf16.bf16 {%0, %1, %2, %3, %4, %5, %6, %7, %8, %9, %10, %11, %12, %13, %14, %15, %16, %17, %18, %19, %20, %21, %22, %23, %24, %25, %26, %27, %28, %29, %30, %31, %32, %33, %34, %35, %36, %37, %38, %39, %40, %41, %42, %43, %44, %45, %46, %47, %48, %49, %50, %51, %52, %53, %54, %55, %56, %57, %58, %59, %60, %61, %62, %63}, da, db, p, 1, 1, 0, 1;\n}\n"
        : "+f"(d[0]), "+f"(d[1]), "+f"(d[2]), "+f"(d[3]), "+f"(d[4]), "+f"(d[5]), "+f"(d[6]), "+f"(d[7]), "+f"(d[8]), "+f"(d[9]), "+f"(d[10]), "+f"(d[11]), "+f"(d[12]), "+f"(d[13]), "+f"(d[14]), "+f"(d[15]), "+f"(d[16]), "+f"(d[17]), "+f"(d[18]), "+f"(d[19]), "+f"(d[20]), "+f"(d[21]), "+f"(d[22]), "+f"(d[23]), "+f"(d[24]), "+f"(d[25]), "+f"(d[26]), "+f"(d[27]), "+f"(d[28]), "+f"(d[29]), "+f"(d[30]), "+f"(d[31]), "+f"(d[32]), "+f"(d[33]), "+f"(d[34]), "+f"(d[35]), "+f"(d[36]), "+f"(d[37]), "+f"(d[38]), "+f"(d[39]), "+f"(d[40]), "+f"(d[41]), "+f"(d[42]), "+f"(d[43]), "+f"(d[44]), "+f"(d[45]), "+f"(d[46]), "+f"(d[47]), "+f"(d[48]), "+f"(d[49]), "+f"(d[50]), "+f"(d[51]), "+f"(d[52]), "+f"(d[53]), "+f"(d[54]), "+f"(d[55]), "+f"(d[56]), "+f"(d[57]), "+f"(d[58]), "+f"(d[59]), "+f"(d[60]), "+f"(d[61]), "+f"(d[62]), "+f"(d[63])
        : "r"(alo), "r"(blo), "r"(scale_d), "n"(AHI), "n"(BHI));
}

template <uint32_t AHI, uint32_t BHI>
__device__ __forceinline__ void wgmma_ss_n160_tb1(float (&d)[80], uint32_t alo, uint32_t blo, int scale_d) {
    asm volatile("{\n.reg .pred p;\n.reg .b64 da, db;\nsetp.ne.b32 p, %82, 0;\nmov.b64 da, {%80, %83};\nmov.b64 db, {%81, %84};\n"
        "wgmma.mma_async.sync.aligned.m64n160k16.f32.bf16.bf16 {%0, %1, %2, %3, %4, %5, %6, %7, %8, %9, %10, %11, %12, %13, %14, %15, %16, %17, %18, %19, %20, %21, %22, %23, %24, %25, %26, %27, %28, %29, %30, %31, %32, %33, %34, %35, %36, %37, %38, %39, %40, %41, %42, %43, %44, %45, %46, %47, %48, %49, %50, %51, %52, %53, %54, %55, %56, %57, %58, %59, %60, %61, %62, %63, %64, %65, %66, %67, %68, %69, %70, %71, %72, %73, %74, %75, %76, %77, %78, %79}, da, db, p, 1, 1, 0, 1;\n}\n"
        : "+f"(d[0]), "+f"(d[1]), "+f"(d[2]), "+f"(d[3]), "+f"(d[4]), "+f"(d[5]), "+f"(d[6]), "+f"(d[7]), "+f"(d[8]), "+f"(d[9]), "+f"(d[10]), "+f"(d[11]), "+f"(d[12]), "+f"(d[13]), "+f"(d[14]), "+f"(d[15]), "+f"(d[16]), "+f"(d[17]), "+f"(d[18]), "+f"(d[19]), "+f"(d[20]), "+f"(d[21]), "+f"(d[22]), "+f"(d[23]), "+f"(d[24]), "+f"(d[25]), "+f"(d[26]), "+f"(d[27]), "+f"(d[28]), "+f"(d[29]), "+f"(d[30]), "+f"(d[31]), "+f"(d[32]), "+f"(d[33]), "+f"(d[34]), "+f"(d[35]), "+f"(d[36]), "+f"(d[37]), "+f"(d[38]), "+f"(d[39]), "+f"(d[40]), "+f"(d[41]), "+f"(d[42]), "+f"(d[43]), "+f"(d[44]), "+f"(d[45]), "+f"(d[46]), "+f"(d[47]), "+f"(d[48]), "+f"(d[49]), "+f"(d[50]), "+f"(d[51]), "+f"(d[52]), "+f"(d[53]), "+f"(d[54]), "+f"(d[55]), "+f"(d[56]), "+f"(d[57]), "+f"(d[58]), "+f"(d[59]), "+f"(d[60]), "+f"(d[61]), "+f"(d[62]), "+f"(d[63]), "+f"(d[64]), "+f"(d[65]), "+f"(d[66]), "+f"(d[67]), "+f"(d[68]), "+f"(d[69]), "+f"(d[70]), "+f"(d[71]), "+f"(d[72]), "+f"(d[73]), "+f"(d[74]), "+f"(d[75]), "+f"(d[76]), "+f"(d[77]), "+f"(d[78]), "+f"(d[79])
        : "r"(alo), "r"(blo), "r"(scale_d), "n"(AHI), "n"(BHI));
}

template <uint32_t AHI, uint32_t BHI>
__device__ __forceinline__ void wgmma_ss_n72_tb1(float (&d)[36], uint32_t alo, uint32_t blo, int scale_d) {
    asm volatile("{\n.reg .pred p;\n.reg .b64 da, db;\nsetp.ne.b32 p, %38, 0;\nmov.b64 da, {%36, %39};\nmov.b64 db, {%37, %40};\n"
        "wgmma.mma_async.sync.aligned.m64n72k16.f32.bf16.bf16 {%0, %1, %2, %3, %4, %5, %6, %7, %8, %9, %10, %11, %12, %13, %14, %15, %16, %17, %18, %19, %20, %21, %22, %23, %24, %25, %26, %27, %28, %29, %30, %31, %32, %33, %34, %35}, da, db, p, 1, 1, 0, 1;\n}\n"
        : "+f"(d[0]), "+f"(d[1]), "+f"(d[2]), "+f"(d[3]), "+f"(d[4]), "+f"(d[5]), "+f"(d[6]), "+f"(d[7]), "+f"(d[8]), "+f"(d[9]), "+f"(d[10]), "+f"(d[11]), "+f"(d[12]), "+f"(d[13]), "+f"(d[14]), "+f"(d[15]), "+f"(d[16]), "+f"(d[17]), "+f"(d[18]), "+f"(d[19]), "+f"(d[20]), "+f"(d[21]), "+f"(d[22]), "+f"(d[23]), "+f"(d[24]), "+f"(d[25]), "+f"(d[26]), "+f"(d[27]), "+f"(d[28]), "+f"(d[29]), "+f"(d[30]), "+f"(d[31]), "+f"(d[32]), "+f"(d[33]), "+f"(d[34]), "+f"(d[35])
        : "r"(alo), "r"(blo), "r"(scale_d), "n"(AHI), "n"(BHI));
}

constexpr int K1_STAGES = 5;
constexpr int K1_A_BYTES = 9 * 16384;
constexpr int K1_SMEM = K1_A_BYTES + K1_STAGES * 16384 + 1024 + 256;
constexpr int K1_UNITS = 11;

__global__ void __cluster_dims__(2, 1, 1) __launch_bounds__(384, 1)
k1_ln_proj(const __grid_constant__ CUtensorMap tm_x, const __grid_constant__ CUtensorMap tm_qkv,
           const __grid_constant__ CUtensorMap tm_g, const __grid_constant__ CUtensorMap tm_u,
           const bf16* __restrict__ wqkv, const bf16* __restrict__ wgate, const bf16* __restrict__ wup) {
    extern __shared__ uint8_t smem_raw[];
    const uint32_t sbase = (smem_u32(smem_raw) + 1023u) & ~1023u;
    const uint32_t sA = sbase, sB = sbase + K1_A_BYTES, sBar = sB + K1_STAGES * 16384;
    const uint32_t xbar = sBar + 192;
    const int tid = threadIdx.x, warp = __shfl_sync(0xffffffffu, tid >> 5, 0), lane = tid & 31, wg = warp >> 2;
    const uint32_t rank = cluster_rank();
    const int mt = blockIdx.x & 15, ng = blockIdx.x >> 4;
    TS(0, wg, 0);
    if (tid == 256) {
        mbar_init(xbar, 1);
        fence_barrier_init();
        mbar_expect_tx(xbar, K1_A_BYTES);
#pragma unroll 1
        for (int i = 0; i < 9; i++) tma_2d(sA + i * 16384, &tm_x, i * 64, mt * 128, xbar);
#pragma unroll 1
        for (int s = 0; s < K1_STAGES; s++) { mbar_init(sBar + 8 * s, 1); mbar_init(sBar + 96 + 8 * s, 8); }
        fence_barrier_init();
    }
    pdl_launch();
    cluster_sync_all();
    if (tid == 256) {
#pragma unroll 1
        for (int kb = 0; kb < K1_STAGES; kb++) {
            mbar_expect_tx(sBar + 8 * kb, 16384);
            tma_2d_mc(sB + kb * 16384 + rank * 8192, &tm_qkv, 216 * ng + (int)rank * 64, kb * 64, sBar + 8 * kb, (uint16_t)3);
        }
    }
    if (warp == 9 && lane < 4) prefetch_l2(reinterpret_cast<const uint8_t*>(wqkv) + (size_t)blockIdx.x * 15552 + lane * 3888, 3888);
    {
        const int g8 = lane >> 3, j = lane & 7;
        TS(0, wg, 40);
        mbar_wait(xbar, 0);
        TS(0, wg, 41);
        if (warp == 9) {
            if (lane >= 4 && lane < 12) prefetch_l2(reinterpret_cast<const uint8_t*>(wgate) + (size_t)blockIdx.x * 41472 + (lane - 4) * 5184, 5184);
            else if (lane >= 12 && lane < 20) prefetch_l2(reinterpret_cast<const uint8_t*>(wup) + (size_t)blockIdx.x * 41472 + (lane - 12) * 5184, 5184);
        }
#pragma unroll 1
        for (int g = warp; g < 32; g += 12) {
            const int row = g * 4 + g8;
            const uint32_t adr = sA + row * 128 + ((j ^ (row & 7)) << 4);
            uint32_t v[9][4];
#pragma unroll
            for (int i = 0; i < 9; i++)
                asm volatile("ld.shared.v4.b32 {%0, %1, %2, %3}, [%4];" : "=r"(v[i][0]), "=r"(v[i][1]), "=r"(v[i][2]), "=r"(v[i][3]) : "r"(adr + i * 16384));
            float s4[4] = {0.f, 0.f, 0.f, 0.f};
#pragma unroll
            for (int i = 0; i < 9; i++)
#pragma unroll
                for (int c = 0; c < 4; c++) { s4[c] += bf_lo(v[i][c]); s4[(c + 2) & 3] += bf_hi(v[i][c]); }
            float sum = (s4[0] + s4[1]) + (s4[2] + s4[3]);
            sum += __shfl_xor_sync(0xffffffffu, sum, 1);
            sum += __shfl_xor_sync(0xffffffffu, sum, 2);
            sum += __shfl_xor_sync(0xffffffffu, sum, 4);
            const float mean = sum * (1.0f / DM);
            const uint32_t mb2 = pack_bf16(mean, mean);
            float f[72];
            float q4[4] = {0.f, 0.f, 0.f, 0.f};
#pragma unroll
            for (int i = 0; i < 9; i++)
#pragma unroll
                for (int c = 0; c < 4; c++) {
                    uint32_t d;
                    asm("sub.rn.bf16x2 %0, %1, %2;" : "=r"(d) : "r"(v[i][c]), "r"(mb2));
                    const float a0 = bf_lo(d), a1 = bf_hi(d);
                    f[8 * i + 2 * c] = a0; f[8 * i + 2 * c + 1] = a1;
                    q4[c] = fmaf(a0, a0, q4[c]); q4[(c + 2) & 3] = fmaf(a1, a1, q4[(c + 2) & 3]);
                }
            float sq = (q4[0] + q4[1]) + (q4[2] + q4[3]);
            sq += __shfl_xor_sync(0xffffffffu, sq, 1);
            sq += __shfl_xor_sync(0xffffffffu, sq, 2);
            sq += __shfl_xor_sync(0xffffffffu, sq, 4);
            const float dm = mean - bf_lo(mb2);
            const float var_b = bf16r(fmaxf(sq * (1.0f / DM) - dm * dm, 0.f));
            const float rden = __fdividef(1.0f, bf16r(sqrt_approx(bf16r(var_b + 1e-5f))));
#pragma unroll
            for (int i = 0; i < 9; i++) {
                uint32_t o[4];
#pragma unroll
                for (int c = 0; c < 4; c++) o[c] = pack_bf16(f[8 * i + 2 * c] * rden, f[8 * i + 2 * c + 1] * rden);
                asm volatile("st.shared.v4.b32 [%0], {%1, %2, %3, %4};" :: "r"(adr + i * 16384), "r"(o[0]), "r"(o[1]), "r"(o[2]), "r"(o[3]) : "memory");
            }
        }
        TS(0, wg, 42);
        fence_proxy_async();
        __syncthreads();
    }

    if (wg == 2) {
        asm volatile("setmaxnreg.dec.sync.aligned.u32 40;");
        if (warp == 8 && lane == 0) {
            int s = 0; uint32_t ph = 0;
#pragma unroll 1
            for (int u = 0; u < K1_UNITS; u++) {
                const CUtensorMap* tm = (u < 2) ? &tm_qkv : (rank ? &tm_u : &tm_g);
                const int col = (u < 2) ? (216 * ng + (u ? 104 : 0) + (int)rank * 64) : (576 * ng + (u - 2) * 64);
#pragma unroll 1
                for (int kb = (u == 0 ? K1_STAGES : 0); kb < 9; kb++) {
                    mbar_wait(sBar + 96 + 8 * s, ph);
                    mbar_expect_tx(sBar + 8 * s, 16384);
                    tma_2d_mc(sB + s * 16384 + rank * 8192, tm, col, kb * 64, sBar + 8 * s, (uint16_t)3);
                    if (++s == K1_STAGES) { s = 0; ph ^= 1; }
                }
            }
        } else if (warp >= 10) {
#pragma unroll 1
            for (int i = 0; i < 16; i++) {
                const int idx = (tid - 320) + 64 * i, hs = 32 + ng * 8 + (idx >> 7);
                bf16* p = g_QKV + (size_t)(hs * 3 + 2) * (SEQ * 8) + (size_t)(mt * 128 + (idx & 127)) * 8;
                *reinterpret_cast<uint32_t*>(p + 2) = (hs < 64) ? 0x3F803F80u : 0x00003F80u;
                *reinterpret_cast<uint2*>(p + 4) = make_uint2((hs < 64) ? 0x00003F80u : 0u, 0u);
            }
            bar_sync(4 + (warp - 10), 160);
            if (lane == 0) signal_counter(&g_cnt_qkv);
            __syncwarp();
            bar_sync(4 + (warp - 10), 160);
            if (lane == 0) signal_counter(&g_cnt_h[mt * 4 + (ng >> 1)]);
        }
        __syncwarp();
        cluster_sync_all();
    } else {
        asm volatile("setmaxnreg.inc.sync.aligned.u32 232;");
        TS(0, wg, 1);
        const int wq = warp & 3, q = lane & 3, rl = lane >> 2;
        const uint32_t dA = desc_lo(sA, 16);
        const uint32_t dB = desc_lo(sB, 8192);
        const int tok0 = mt * 128 + wq * 16 + rl;
#pragma unroll 1
        for (int u = wg; u < K1_UNITS; u += 2) {
            int it = u * 9;
            int s = it % K1_STAGES; uint32_t ph = (it / K1_STAGES) & 1;
            if (u > 0) bar_sync(1 + wg, 256);
            TS(0, wg, 2 + 3 * u);
            if (u < 2) {
                float acc0[56], acc1[56];
#pragma unroll
                for (int i = 0; i < 56; i++) { acc0[i] = 0.f; acc1[i] = 0.f; }
                int sprev = 0;
#pragma unroll 1
                for (int kb = 0; kb < 9; kb++) {
                    mbar_wait(sBar + 8 * s, ph);
                    WG_FENCE();
#pragma unroll
                    for (int k = 0; k < 4; k++) {
                        const uint32_t da = dA + kb * 1024 + k * 2, db = dB + s * 1024 + k * 128;
                        wgmma_ss_n112_tb1<HI_SW128, HI_SW128>(acc0, da, db, 1);
                        wgmma_ss_n112_tb1<HI_SW128, HI_SW128>(acc1, da + 512, db, 1);
                    }
                    WG_COMMIT();
                    if (kb == 7) bar_arrive(1 + (wg ^ 1), 256);
                    if (kb > 0) { WG_WAIT(1); if (lane == 0) { mbar_arrive(sBar + 96 + 8 * sprev); mbar_arrive_remote(sBar + 96 + 8 * sprev, rank ^ 1); } }
                    sprev = s;
                    if (++s == K1_STAGES) { s = 0; ph ^= 1; }
                }
                WG_WAIT(0);
                fence_regs(acc0); fence_regs(acc1);
                if (lane == 0) { mbar_arrive(sBar + 96 + 8 * sprev); mbar_arrive_remote(sBar + 96 + 8 * sprev, rank ^ 1); }
                TS(0, wg, 3 + 3 * u);
                int c0 = 216 * ng + (u ? 104 : 0) + 2 * q;
                asm volatile("" : "+r"(c0));
                int hs = c0 / 18, d = c0 - hs * 18;
                const float qscale = 0.23570226039551584f * 1.4426950408889634f;
#pragma unroll
                for (int j = 0; j < 14; j++) {
                    bf16* p = g_QKV + (size_t)(hs * 49152 + (d >> 3) * 16384 + (d & 7) + tok0 * 8);
                    const float sc = (hs < 32) ? qscale : 1.0f;
                    *reinterpret_cast<uint32_t*>(p) = pack_bf16(acc0[4 * j] * sc, acc0[4 * j + 1] * sc);
                    *reinterpret_cast<uint32_t*>(p + 64) = pack_bf16(acc0[4 * j + 2] * sc, acc0[4 * j + 3] * sc);
                    *reinterpret_cast<uint32_t*>(p + 512) = pack_bf16(acc1[4 * j] * sc, acc1[4 * j + 1] * sc);
                    *reinterpret_cast<uint32_t*>(p + 576) = pack_bf16(acc1[4 * j + 2] * sc, acc1[4 * j + 3] * sc);
                    d += 8; if (d >= 18) { d -= 18; hs++; }
                }
                bar_arrive(4 + wg, 160);
            } else {
                float acc0[64], acc1[64];
#pragma unroll
                for (int i = 0; i < 64; i++) { acc0[i] = 0.f; acc1[i] = 0.f; }
                int sprev = 0;
#pragma unroll 1
                for (int kb = 0; kb < 9; kb++) {
                    mbar_wait(sBar + 8 * s, ph);
                    WG_FENCE();
#pragma unroll
                    for (int k = 0; k < 4; k++) {
                        const uint32_t da = dA + kb * 1024 + k * 2, db = dB + s * 1024 + k * 128;
                        wgmma_ss_n128_tb1<HI_SW128, HI_SW128>(acc0, da, db, 1);
                        wgmma_ss_n128_tb1<HI_SW128, HI_SW128>(acc1, da + 512, db, 1);
                    }
                    WG_COMMIT();
                    if (kb == 7 && u + 1 < K1_UNITS) bar_arrive(1 + (wg ^ 1), 256);
                    if (kb > 0) { WG_WAIT(1); if (lane == 0) { mbar_arrive(sBar + 96 + 8 * sprev); mbar_arrive_remote(sBar + 96 + 8 * sprev, rank ^ 1); } }
                    sprev = s;
                    if (++s == K1_STAGES) { s = 0; ph ^= 1; }
                }
                WG_WAIT(0);
                fence_regs(acc0); fence_regs(acc1);
                if (lane == 0) { mbar_arrive(sBar + 96 + 8 * sprev); mbar_arrive_remote(sBar + 96 + 8 * sprev, rank ^ 1); }
                TS(0, wg, 3 + 3 * u);
                int fbase = 576 * ng + (u - 2) * 64 + q * 8;
                asm volatile("" : "+r"(fbase));
                bf16* hp = g_H + (size_t)tok0 * FF + fbase;
#pragma unroll
                for (int mh = 0; mh < 2; mh++) {
#pragma unroll
                    for (int h = 0; h < 2; h++) {
#pragma unroll
                        for (int g32 = 0; g32 < 2; g32++) {
                            uint32_t o[4];
#pragma unroll
                            for (int j4 = 0; j4 < 4; j4++) {
                                const int i0 = 4 * (g32 * 4 + j4) + 2 * h;
                                const uint32_t gp = mh ? pack_bf16(acc1[i0], acc1[i0 + 1]) : pack_bf16(acc0[i0], acc0[i0 + 1]);
                                const uint32_t up = mh ? pack_bf16(acc1[32 + i0], acc1[32 + i0 + 1]) : pack_bf16(acc0[32 + i0], acc0[32 + i0 + 1]);
                                const uint32_t sp = pack_bf16(silu_f(bf_lo(gp)), silu_f(bf_hi(gp)));
                                o[j4] = pack_bf16(bf_lo(sp) * bf_lo(up), bf_hi(sp) * bf_hi(up));
                            }
                            *reinterpret_cast<uint4*>(hp + (size_t)(mh * 64 + h * 8) * FF + g32 * 32) = make_uint4(o[0], o[1], o[2], o[3]);
                        }
                    }
                }
            }
            TS(0, wg, 4 + 3 * u);
        }
        bar_arrive(4 + wg, 160);
        cluster_sync_all();
    }
}

constexpr int K2_SMEM = 2 * 98304 + 512 * 48 + 1024 + 64;

__device__ __forceinline__ float exp2_poly(float x) {
    float y;
    asm("fma.rn.sat.f32 %0, %1, %2, %3;" : "=f"(y) : "f"(x), "f"(1.0f / 230.0f), "f"(126.0f / 230.0f));
    const float t = fmaf(y, 230.0f, 12582912.0f - 126.0f);
    const float r = t - (12582912.0f - 126.0f);
    const float f = fmaf(y, 230.0f, -r);
    float p = fmaf(f, 0.0551716685f, 0.2426111251f);
    p = fmaf(p, f, 0.6932609677f);
    p = fmaf(p, f, 0.9999280572f);
    return __uint_as_float(__float_as_uint(p) + (__float_as_uint(t) << 23));
}
__device__ __forceinline__ float lg2(float x) { float y; asm("lg2.approx.ftz.f32 %0, %1;" : "=f"(y) : "f"(x)); return y; }
__device__ __forceinline__ float split3(float v, uint32_t& hm, uint32_t& l0) {
    const float h = bf16r(v), md = bf16r(v - h), lo = bf16r(v - h - md);
    hm = pack_bf16(-h, -md); l0 = pack_bf16(-lo, 0.f);
    return (h + md) + lo;
}
#define K2_PMASK 0x4444
#define K2_POLY(i) ((K2_PMASK >> ((i) & 15)) & 1)

__global__ void __launch_bounds__(512, 1)
k2_attn(const bf16* __restrict__ wdown, const bf16* __restrict__ wout) {
    extern __shared__ uint8_t smem_raw[];
    const uint32_t sbase = (smem_u32(smem_raw) + 1023u) & ~1023u;
    const uint32_t sK = sbase, sV = sbase + 98304, sQ = sbase + 2 * 98304, sBar = sQ + 512 * 48, sFlag = sBar + 32;
    const int tid = threadIdx.x, warp = __shfl_sync(0xffffffffu, tid >> 5, 0), lane = tid & 31, wg = warp >> 2;
    const int head = blockIdx.x >> 2, qb = blockIdx.x & 3;
    TS(1, wg, 0);
    pdl_launch();
    if (tid == 0) {
        for (int g = 0; g < 4; g++) mbar_init(sBar + 8 * g, 1);
        fence_barrier_init();
    }
    if (tid == 0) {
        wait_counter(&g_cnt_qkv, (read_epoch() + 1u) * 256u);
        asm volatile("fence.proxy.async;" ::: "memory");
        mbar_expect_tx(sBar, 6 * 320 * 16);
#pragma unroll 1
        for (int c = 0; c < 3; c++) {
            const size_t off = (size_t)(head * 3 + c) * SEQ * 8;
            bulk_g2s(sK + c * 32768, g_QKV + (size_t)32 * 49152 + off, 320 * 16, sBar);
            bulk_g2s(sV + c * 32768, g_QKV + (size_t)64 * 49152 + off, 320 * 16, sBar);
        }
    }
    if (tid < 4) asm volatile("st.shared.u32 [%0], %1;" :: "r"(sFlag + 4 * tid), "r"(0u) : "memory");
    __syncthreads();
    TS(1, wg, 10);
    const int wq = warp & 3, q = lane & 3, rl = lane >> 2;
    const uint32_t dK0 = desc_lo(sK, 32768);
    const uint32_t dK1 = desc_lo(sK + 65536, 0);
    const uint32_t dV = desc_lo(sV, 128);
    {
        const bf16* qp = g_QKV + (size_t)head * 3 * SEQ * 8;
#pragma unroll
        for (int qt = 0; qt < 2; qt++) {
            const int r0 = qb * 512 + (qt * 4 + wg) * 64 + wq * 16 + rl, r1 = r0 + 8;
            const uint32_t a0 = __ldcg(reinterpret_cast<const uint32_t*>(qp + (size_t)r0 * 8 + 2 * q));
            const uint32_t a1 = __ldcg(reinterpret_cast<const uint32_t*>(qp + (size_t)r1 * 8 + 2 * q));
            const uint32_t a2 = __ldcg(reinterpret_cast<const uint32_t*>(qp + (size_t)(SEQ + r0) * 8 + 2 * q));
            const uint32_t a3 = __ldcg(reinterpret_cast<const uint32_t*>(qp + (size_t)(SEQ + r1) * 8 + 2 * q));
            uint32_t b0 = 0, b1 = 0;
            if (q == 0) {
                b0 = __ldcg(reinterpret_cast<const uint32_t*>(qp + (size_t)(2 * SEQ + r0) * 8));
                b1 = __ldcg(reinterpret_cast<const uint32_t*>(qp + (size_t)(2 * SEQ + r1) * 8));
            }
            asm volatile("st.shared.v4.b32 [%0], {%1, %2, %3, %4};" :: "r"(sQ + qt * 8192 + tid * 16), "r"(a0), "r"(a1), "r"(a2), "r"(a3) : "memory");
            asm volatile("st.shared.v2.b32 [%0], {%1, %2};" :: "r"(sQ + 16384 - 8192 + qt * 4096 + tid * 8 + 8192), "r"(b0), "r"(b1) : "memory");
        }
    }
    if (tid == 0) {
#pragma unroll 1
        for (int g = 1; g < 3; g++) {
            const int k0 = (g == 1) ? 320 : 1088, k1 = (g == 1) ? 1088 : 2048;
            const uint32_t bytes = (k1 - k0) * 16;
            mbar_expect_tx(sBar + 8 * g, 6 * bytes);
#pragma unroll 1
            for (int c = 0; c < 3; c++) {
                const size_t off = ((size_t)(head * 3 + c) * SEQ + k0) * 8;
                bulk_g2s(sK + c * 32768 + k0 * 16, g_QKV + (size_t)32 * 49152 + off, bytes, sBar + 8 * g);
                bulk_g2s(sV + c * 32768 + k0 * 16, g_QKV + (size_t)64 * 49152 + off, bytes, sBar + 8 * g);
            }
        }
    }
    if (warp == 1) {
        if (lane < 8) prefetch_l2(reinterpret_cast<const uint8_t*>(wdown) + (size_t)blockIdx.x * 41472 + lane * 5184, 5184);
        else if (lane == 8) prefetch_l2(reinterpret_cast<const uint8_t*>(wout) + (size_t)blockIdx.x * 5184, 5184);
    }
    TS(1, wg, 11);
    bool first_pass = true, safe = false;
#pragma unroll 1
    for (int qt = 0; qt < 2;) {
        const int r0 = qb * 512 + (qt * 4 + wg) * 64 + wq * 16 + rl, r1 = r0 + 8;
        uint32_t qa0, qa1, qa2, qa3, qb0, qb1;
        asm volatile("ld.shared.v4.b32 {%0, %1, %2, %3}, [%4];" : "=r"(qa0), "=r"(qa1), "=r"(qa2), "=r"(qa3) : "r"(sQ + qt * 8192 + tid * 16));
        asm volatile("ld.shared.v2.b32 {%0, %1}, [%2];" : "=r"(qb0), "=r"(qb1) : "r"(sQ + 16384 + qt * 4096 + tid * 8));
        const uint32_t qz = 0;
        float o[12];
#pragma unroll
        for (int i = 0; i < 12; i++) o[i] = 0.f;
        float m0 = 0.f, m1 = 0.f;
        float sa[32], sb[32];
        uint32_t p[16];
        bool bad = false, need = true;

        auto refresh = [&](float (&sc)[32], bool first) {
            const float l0 = __shfl_sync(0xffffffffu, o[8], (lane & ~3) | 1);
            const float l1 = __shfl_sync(0xffffffffu, o[10], (lane & ~3) | 1);
            bad = bad || !(l0 <= 1.2676506002282294e30f && l1 <= 1.2676506002282294e30f);
            float x0 = sc[0], x1 = sc[2];
#pragma unroll
            for (int i = 0; i < 8; i++) {
                x0 = fmaxf(x0, fmaxf(sc[4 * i], sc[4 * i + 1]));
                x1 = fmaxf(x1, fmaxf(sc[4 * i + 2], sc[4 * i + 3]));
            }
            x0 = fmaxf(x0, __shfl_xor_sync(0xffffffffu, x0, 1)); x0 = fmaxf(x0, __shfl_xor_sync(0xffffffffu, x0, 2));
            x1 = fmaxf(x1, __shfl_xor_sync(0xffffffffu, x1, 1)); x1 = fmaxf(x1, __shfl_xor_sync(0xffffffffu, x1, 2));
            if (!first) {
                x0 = fmaxf(x0, 0.f); x1 = fmaxf(x1, 0.f);
                if (!safe) { x0 = fmaxf(x0, lg2(l0)); x1 = fmaxf(x1, lg2(l1)); }
            }
            uint32_t hm0, lo0, hm1, lo1;
            const float n0 = split3(m0 + x0, hm0, lo0), n1 = split3(m1 + x1, hm1, lo1);
            const float d0 = n0 - m0, d1 = n1 - m1;
            m0 = n0; m1 = n1;
            if (q == 1) { qb0 = hm0; qb1 = hm1; }
            if (q == 2) { qb0 = lo0; qb1 = lo1; }
            const float a0 = first ? 0.f : ex2(-d0), a1 = first ? 0.f : ex2(-d1);
#pragma unroll
            for (int i = 0; i < 3; i++) { o[4 * i] *= a0; o[4 * i + 1] *= a0; o[4 * i + 2] *= a1; o[4 * i + 3] *= a1; }
#pragma unroll
            for (int i = 0; i < 8; i++) { sc[4 * i] -= d0; sc[4 * i + 1] -= d0; sc[4 * i + 2] -= d1; sc[4 * i + 3] -= d1; }
        };
        auto issue_qk = [&](float (&sc)[32], int j) {
            WG_FENCE();
            wgmma_rs_n64_tb0<HI_K>(sc, qa0, qa1, qa2, qa3, dK0 + j * 64, 0);
            wgmma_rs_n64_tb0<HI_K>(sc, qb0, qb1, qz, qz, dK1 + j * 64, 1);
            WG_COMMIT();
        };
        auto exp_pv = [&](float (&sc)[32], int j) {
#pragma unroll
            for (int t = 0; t < 4; t++) {
#pragma unroll
                for (int i = 0; i < 4; i++) {
                    const int e = 8 * t + 2 * i;
                    p[4 * t + i] = pack_bf16(K2_POLY(e) ? exp2_poly(sc[e]) : ex2(sc[e]), K2_POLY(e + 1) ? exp2_poly(sc[e + 1]) : ex2(sc[e + 1]));
                    asm volatile("" : "+r"(p[4 * t + i]) :: "memory");
                }
                WG_FENCE();
                wgmma_rs_n24_tb1<HI_V>(o, p[4 * t], p[4 * t + 1], p[4 * t + 2], p[4 * t + 3], dV + j * 64 + t * 16, 1);
            }
            WG_COMMIT();
        };

        if (first_pass) mbar_wait(sBar, 0);
        TS(1, wg, 12 + qt);
        issue_qk(sa, 0);
        WG_WAIT(0);
        fence_regs(sa);
        if (safe) {
#pragma unroll 1
            for (int j = 0; j < 32; j++) {
                refresh(sa, j == 0);
                exp_pv(sa, j);
                issue_qk(sa, min(j + 1, 31));
                WG_WAIT(0);
                fence_regs(sa); fence_regs(o);
            }
        } else {
#pragma unroll 1
            for (int seg = 0; seg < 8; seg++) {
                if (first_pass && (seg == 1 || seg == 4)) mbar_wait(sBar + (seg == 1 ? 8 : 16), 0);
                if (need) refresh(sa, seg == 0);
#pragma unroll 1
                for (int j = 4 * seg; j < 4 * seg + 4; j += 2) {
                    issue_qk(sb, j + 1);
                    exp_pv(sa, j);
                    WG_WAIT(0);
                    fence_regs(sb);
                    issue_qk(sa, min(j + 2, 31));
                    exp_pv(sb, j + 1);
                    WG_WAIT(0);
                    fence_regs(sa); fence_regs(o);
                }
                const bool grown = (q == 1) && !(o[8] <= 1048576.f && o[10] <= 1048576.f);
                need = __any_sync(0xffffffffu, grown);
            }
        }
        WG_WAIT(0);
        fence_regs(o);
        first_pass = false;
        const float l0 = __shfl_sync(0xffffffffu, o[8], (lane & ~3) | 1);
        const float l1 = __shfl_sync(0xffffffffu, o[10], (lane & ~3) | 1);
        if (!safe) {
            bad = bad || !(l0 <= 1.2676506002282294e30f && l1 <= 1.2676506002282294e30f);
#pragma unroll
            for (int i = 0; i < 12; i++) bad = bad || !(fabsf(o[i]) <= 3.0e38f);
            if (__any_sync(0xffffffffu, bad) && lane == 0) asm volatile("st.shared.u32 [%0], %1;" :: "r"(sFlag + 4 * wg), "r"(1u) : "memory");
            bar_sync(1 + wg, 128);
            uint32_t fl;
            asm volatile("ld.shared.u32 %0, [%1];" : "=r"(fl) : "r"(sFlag + 4 * wg) : "memory");
            bar_sync(1 + wg, 128);
            if (fl) {
                if ((tid & 127) == 0) asm volatile("st.shared.u32 [%0], %1;" :: "r"(sFlag + 4 * wg), "r"(0u) : "memory");
                safe = true;
                continue;
            }
        }
        const float i0 = __fdividef(1.0f, l0), i1 = __fdividef(1.0f, l1);
        bf16* op0 = g_O + (size_t)r0 * DM + head * DH + 2 * q;
        bf16* op1 = g_O + (size_t)r1 * DM + head * DH + 2 * q;
        *reinterpret_cast<uint32_t*>(op0) = pack_bf16(o[0] * i0, o[1] * i0);
        *reinterpret_cast<uint32_t*>(op1) = pack_bf16(o[2] * i1, o[3] * i1);
        *reinterpret_cast<uint32_t*>(op0 + 8) = pack_bf16(o[4] * i0, o[5] * i0);
        *reinterpret_cast<uint32_t*>(op1 + 8) = pack_bf16(o[6] * i1, o[7] * i1);
        if (q == 0) {
            *reinterpret_cast<uint32_t*>(op0 + 16) = pack_bf16(o[8] * i0, o[9] * i0);
            *reinterpret_cast<uint32_t*>(op1 + 16) = pack_bf16(o[10] * i1, o[11] * i1);
        }
        TS(1, wg, 1 + qt);
        safe = false;
        qt++;
    }
}

constexpr int K3_STAGES = 4;
constexpr int K3_STAGE_BYTES = 16384 + 36864;
constexpr int K3_SMEM = K3_STAGES * K3_STAGE_BYTES + 1024 + 256;

__global__ void __cluster_dims__(2, 1, 1) __launch_bounds__(384, 1)
k3_down_out(const __grid_constant__ CUtensorMap tm_h, const __grid_constant__ CUtensorMap tm_wd,
            const __grid_constant__ CUtensorMap tm_o, const __grid_constant__ CUtensorMap tm_wo,
            const bf16* __restrict__ x, bf16* __restrict__ out) {
    extern __shared__ uint8_t smem_raw[];
    const uint32_t sbase = (smem_u32(smem_raw) + 1023u) & ~1023u;
    const uint32_t sBar = sbase + K3_STAGES * K3_STAGE_BYTES;
    const int tid = threadIdx.x, warp = __shfl_sync(0xffffffffu, tid >> 5, 0), lane = tid & 31, wg = warp >> 2;
    const uint32_t rank = cluster_rank();
    const int mt = blockIdx.x & 15, nt = (blockIdx.x >> 4) & 1, ks = blockIdx.x >> 5;
    TS(2, wg, 0);
    if (tid == 0) {
        for (int s = 0; s < K3_STAGES; s++) { mbar_init(sBar + 8 * s, 1); mbar_init(sBar + 64 + 8 * s, 16); }
        fence_barrier_init();
    }
    const unsigned int epoch1 = read_epoch() + 1u;
    if (tid == 256) {
        wait_counter(&g_cnt_h[mt * 4 + ks], epoch1 * 4u);
        asm volatile("fence.proxy.async;" ::: "memory");
    }
    cluster_sync_all();

    if (wg == 2) {
        asm volatile("setmaxnreg.dec.sync.aligned.u32 40;");
        if (warp == 8 && lane == 0) {
            prefetch_tmap(&tm_h); prefetch_tmap(&tm_wd); prefetch_tmap(&tm_o); prefetch_tmap(&tm_wo);
            int s = 0; uint32_t ph = 1;
#pragma unroll 1
            for (int it = 0; it < 27; it++) {
                if (it == 18) pdl_wait();
                const uint32_t sa = sbase + s * K3_STAGE_BYTES, sb = sa + 16384, full = sBar + 8 * s;
                mbar_wait(sBar + 64 + 8 * s, ph);
                if (it < 18) {
                    const int kb = ks * 18 + it;
                    mbar_expect_tx(full, 16384 + 36864);
                    tma_2d(sa, &tm_h, kb * 64, mt * 128, full);
                    const int b0 = rank ? 5 : 0, b1 = rank ? 9 : 5;
                    _Pragma("unroll 1") for (int b = b0; b < b1; b++) tma_5d_mc(sb + b * 4096, &tm_wd, nt * 288 + b * 32, kb * 2, full, (uint16_t)3);
                } else {
                    const int kb = it - 18;
                    mbar_expect_tx(full, 16384 + 12288);
                    tma_2d(sa, &tm_o, kb * 64, mt * 128, full);
                    const int b0 = rank ? 2 : 0, b1 = rank ? 3 : 2;
                    _Pragma("unroll 1") for (int b = b0; b < b1; b++) tma_2d_mc(sb + b * 4096, &tm_wo, nt * 288 + ks * 72 + b * 32, kb * 64, full, (uint16_t)3);
                }
                if (++s == K3_STAGES) { s = 0; ph ^= 1; }
            }
        } else if (warp == 9) {
            const int tile = mt * 2 + nt;
            bar_sync(2, 288);
            if (lane == 0) {
                __threadfence();
                atomicAdd(&g_cnt[tile], 1u);
#pragma unroll 1
                for (uint32_t n = 0; n < (1u << 24); n++) {
                    uint32_t v;
                    asm volatile("ld.acquire.gpu.global.u32 %0, [%1];" : "=r"(v) : "l"(&g_cnt[tile]) : "memory");
                    if ((int)(v - epoch1 * 4u) >= 0) break;
                }
                __threadfence();
            }
            __syncwarp();
            bar_arrive(1, 288);
        }
        __syncwarp();
        cluster_sync_all();
    } else {
        asm volatile("setmaxnreg.inc.sync.aligned.u32 232;");
        const int wq = warp & 3, q = lane & 3, rl = lane >> 2;
        const uint32_t dA = desc_lo(sbase + wg * 8192, 16);
        const uint32_t dB = desc_lo(sbase + 16384, 4096);
        float fa[80], fb[64], sa[36];
        int s = 0, sprev = 0; uint32_t ph = 0;
#pragma unroll 1
        for (int it = 0; it < 18; it++) {
            mbar_wait(sBar + 8 * s, ph);
            TS(2, wg, 10 + it);
            WG_FENCE();
#pragma unroll
            for (int k = 0; k < 4; k++) {
                const uint32_t so = s * (K3_STAGE_BYTES >> 4);
                wgmma_ss_n160_tb1<HI_SW128, HI_SW64>(fa, dA + so + k * 2, dB + so + k * 64, (it | k) != 0);
                wgmma_ss_n128_tb1<HI_SW128, HI_SW64>(fb, dA + so + k * 2, dB + so + k * 64 + 1280, (it | k) != 0);
            }
            WG_COMMIT();
            if (it > 0) { WG_WAIT(1); if (lane == 0) { mbar_arrive(sBar + 64 + 8 * sprev); mbar_arrive_remote(sBar + 64 + 8 * sprev, rank ^ 1); } }
            sprev = s;
            if (++s == K3_STAGES) { s = 0; ph ^= 1; }
        }
        WG_WAIT(0);
        fence_regs(fa); fence_regs(fb);
        if (lane == 0) { mbar_arrive(sBar + 64 + 8 * sprev); mbar_arrive_remote(sBar + 64 + 8 * sprev, rank ^ 1); }
        TS(2, wg, 1);
        const int tile = mt * 2 + nt;
        float own[36];
        uint32_t xv[18];
        const size_t xoff = (size_t)(mt * 128 + wg * 64 + wq * 16 + rl) * DM + nt * 288 + ks * 72 + 2 * q;
        uint4* const part = reinterpret_cast<uint4*>(g_part);
#pragma unroll
        for (int i = 0; i < 36; i++) sa[i] = 0.f;
#pragma unroll
        for (int it = 0; it < 9; it++) {
            mbar_wait(sBar + 8 * s, ph);
            WG_FENCE();
#pragma unroll
            for (int k = 0; k < 4; k++) {
                const uint32_t so = s * (K3_STAGE_BYTES >> 4);
                wgmma_ss_n72_tb1<HI_SW128, HI_SW64>(sa, dA + so + k * 2, dB + so + k * 64, 1);
            }
            WG_COMMIT();
            if (it < 4) {
                const int qd = it;
                float v[36];
#pragma unroll
                for (int i = 0; i < 36; i++) {
                    const int idx = qd * 36 + i;
                    v[i] = (idx < 80) ? fa[idx < 80 ? idx : 0] : fb[idx >= 80 ? idx - 80 : 0];
                }
                if (qd == ks) {
#pragma unroll
                    for (int i = 0; i < 36; i++) own[i] = v[i];
                } else {
                    float mx = 0.f;
#pragma unroll
                    for (int i = 0; i < 36; i++) mx = fmaxf(mx, fabsf(v[i]));
                    const int eb = min(max((int)(__float_as_uint(mx) >> 23), 16), 240);
                    const float sc = __uint_as_float((uint32_t)(268 - eb) << 23);
                    uint32_t w[20];
#pragma unroll
                    for (int i = 0; i < 18; i++) {
                        const __half2 h2 = __floats2half2_rn(v[2 * i] * sc, v[2 * i + 1] * sc);
                        w[i] = *reinterpret_cast<const uint32_t*>(&h2);
                    }
                    w[18] = (uint32_t)(eb - 14) << 23;
                    w[19] = 0u;
                    uint4* dst = part + ((size_t)((tile * 4 + ks) * 4 + qd) * 5) * 256 + tid;
#pragma unroll
                    for (int i = 0; i < 5; i++) __stcg(dst + i * 256, make_uint4(w[4 * i], w[4 * i + 1], w[4 * i + 2], w[4 * i + 3]));
                }
                if (it == 3) bar_arrive(2, 288);
            }
            if (it > 0) { WG_WAIT(1); if (lane == 0) { mbar_arrive(sBar + 64 + 8 * sprev); mbar_arrive_remote(sBar + 64 + 8 * sprev, rank ^ 1); } }
            sprev = s;
            if (++s == K3_STAGES) { s = 0; ph ^= 1; }
        }
        TS(2, wg, 2);
#pragma unroll
        for (int h = 0; h < 2; h++)
#pragma unroll
            for (int t = 0; t < 9; t++) xv[h * 9 + t] = __ldg(reinterpret_cast<const uint32_t*>(x + xoff + (size_t)h * 8 * DM + 8 * t));
        TS(2, wg, 3);
        bar_sync(1, 288);
        TS(2, wg, 4);
        {
            uint4 v[3][5];
#pragma unroll
            for (int d = 0; d < 3; d++) {
                const int src = (ks + 1 + d) & 3;
                const uint4* p = part + ((size_t)((tile * 4 + src) * 4 + ks) * 5) * 256 + tid;
#pragma unroll
                for (int i = 0; i < 5; i++) v[d][i] = __ldcg(p + i * 256);
            }
#pragma unroll
            for (int d = 0; d < 3; d++) {
                const float isc = __uint_as_float(v[d][4].z);
#pragma unroll
                for (int i = 0; i < 18; i++) {
                    const uint32_t wv = (i & 3) == 0 ? v[d][i >> 2].x : ((i & 3) == 1 ? v[d][i >> 2].y : ((i & 3) == 2 ? v[d][i >> 2].z : v[d][i >> 2].w));
                    const float2 f2 = __half22float2(*reinterpret_cast<const __half2*>(&wv));
                    own[2 * i] = fmaf(f2.x, isc, own[2 * i]); own[2 * i + 1] = fmaf(f2.y, isc, own[2 * i + 1]);
                }
            }
        }
        WG_WAIT(0);
        fence_regs(sa);
#pragma unroll
        for (int h = 0; h < 2; h++) {
#pragma unroll
            for (int t = 0; t < 9; t++) {
                const uint32_t fp = pack_bf16(own[4 * t + 2 * h], own[4 * t + 2 * h + 1]);
                const uint32_t gp = pack_bf16(silu_f(bf_lo(fp)), silu_f(bf_hi(fp)));
                const uint32_t sp = pack_bf16(sa[4 * t + 2 * h], sa[4 * t + 2 * h + 1]);
                const uint32_t mp = pack_bf16(bf_lo(sp) * bf_lo(gp), bf_hi(sp) * bf_hi(gp));
                *reinterpret_cast<uint32_t*>(out + xoff + (size_t)h * 8 * DM + 8 * t) =
                    pack_bf16(bf_lo(xv[h * 9 + t]) + bf_lo(mp), bf_hi(xv[h * 9 + t]) + bf_hi(mp));
            }
        }
        TS(2, wg, 5);
        if (tid == 0) {
            __threadfence();
            if (atomicAdd(&g_done, 1u) == epoch1 * 128u - 1u) atomicAdd(&g_epoch, 1u);
        }
        cluster_sync_all();
    }
}

typedef CUresult (*EncodeTiledFn)(CUtensorMap*, CUtensorMapDataType, cuuint32_t, void*, const cuuint64_t*, const cuuint64_t*,
                                  const cuuint32_t*, const cuuint32_t*, CUtensorMapInterleave, CUtensorMapSwizzle,
                                  CUtensorMapL2promotion, CUtensorMapFloatOOBfill);

struct HostState {
    bool ready;
    const void* key[7];
    CUtensorMap tm_x, tm_qkv, tm_g, tm_u, tm_h, tm_wd, tm_o, tm_wo;
};
HostState g_hs;

void encode_2d(EncodeTiledFn fn, CUtensorMap* tm, const void* ptr, uint64_t inner, uint64_t outer, uint32_t box_in, uint32_t box_out,
               CUtensorMapSwizzle swz) {
    cuuint64_t dims[2] = {inner, outer};
    cuuint64_t strides[1] = {inner * 2};
    cuuint32_t box[2] = {box_in, box_out};
    cuuint32_t es[2] = {1, 1};
    fn(tm, CU_TENSOR_MAP_DATA_TYPE_BFLOAT16, 2, const_cast<void*>(ptr), dims, strides, box, es, CU_TENSOR_MAP_INTERLEAVE_NONE, swz,
       CU_TENSOR_MAP_L2_PROMOTION_L2_128B, CU_TENSOR_MAP_FLOAT_OOB_FILL_NONE);
}

}

extern "C" void kernel_launch(void* const* d_in, const int* in_sizes, int n_in, void* d_out, int out_size) {
    const bf16* x = (const bf16*)d_in[0];
    const bf16* wqkv = (const bf16*)d_in[1];
    const bf16* wo = (const bf16*)d_in[2];
    const bf16* wg = (const bf16*)d_in[4];
    const bf16* wu = (const bf16*)d_in[5];
    const bf16* wd = (const bf16*)d_in[6];
    bf16* out = (bf16*)d_out;

    bool same = g_hs.ready;
    for (int i = 0; i < 7 && same; i++) same = (g_hs.key[i] == d_in[i]);
    if (!same) {
        void* fnp = nullptr;
        cudaDriverEntryPointQueryResult qr;
        cudaGetDriverEntryPoint("cuTensorMapEncodeTiled", &fnp, cudaEnableDefault, &qr);
        EncodeTiledFn fn = (EncodeTiledFn)fnp;
        void *pH = nullptr, *pO = nullptr;
        cudaGetSymbolAddress(&pH, g_H);
        cudaGetSymbolAddress(&pO, g_O);
        encode_2d(fn, &g_hs.tm_x, x, DM, SEQ, 64, 128, CU_TENSOR_MAP_SWIZZLE_128B);
        encode_2d(fn, &g_hs.tm_qkv, wqkv, 3 * DM, DM, 64, 64, CU_TENSOR_MAP_SWIZZLE_128B);
        encode_2d(fn, &g_hs.tm_g, wg, FF, DM, 64, 64, CU_TENSOR_MAP_SWIZZLE_128B);
        encode_2d(fn, &g_hs.tm_u, wu, FF, DM, 64, 64, CU_TENSOR_MAP_SWIZZLE_128B);
        encode_2d(fn, &g_hs.tm_h, pH, FF, SEQ, 64, 128, CU_TENSOR_MAP_SWIZZLE_128B);
        encode_2d(fn, &g_hs.tm_o, pO, DM, SEQ, 64, 128, CU_TENSOR_MAP_SWIZZLE_128B);
        encode_2d(fn, &g_hs.tm_wo, wo, DM, DM, 32, 64, CU_TENSOR_MAP_SWIZZLE_64B);
        {
            cuuint64_t dims[5] = {(cuuint64_t)DM, 2, 4, 4, (cuuint64_t)(FF / 32)};
            cuuint64_t strides[4] = {(cuuint64_t)DM * 2, (cuuint64_t)DM * 2 * 8, (cuuint64_t)DM * 2 * 2, (cuuint64_t)DM * 2 * 32};
            cuuint32_t box[5] = {32, 2, 4, 4, 2};
            cuuint32_t es[5] = {1, 1, 1, 1, 1};
            fn(&g_hs.tm_wd, CU_TENSOR_MAP_DATA_TYPE_BFLOAT16, 5, const_cast<bf16*>(wd), dims, strides, box, es,
               CU_TENSOR_MAP_INTERLEAVE_NONE, CU_TENSOR_MAP_SWIZZLE_64B, CU_TENSOR_MAP_L2_PROMOTION_L2_128B, CU_TENSOR_MAP_FLOAT_OOB_FILL_NONE);
        }
        cudaFuncSetAttribute(k1_ln_proj, cudaFuncAttributeMaxDynamicSharedMemorySize, K1_SMEM);
        cudaFuncSetAttribute(k2_attn, cudaFuncAttributeMaxDynamicSharedMemorySize, K2_SMEM);
        cudaFuncSetAttribute(k3_down_out, cudaFuncAttributeMaxDynamicSharedMemorySize, K3_SMEM);
        for (int i = 0; i < 7; i++) g_hs.key[i] = d_in[i];
        g_hs.ready = true;
    }
    k1_ln_proj<<<128, 384, K1_SMEM>>>(g_hs.tm_x, g_hs.tm_qkv, g_hs.tm_g, g_hs.tm_u, wqkv, wg, wu);
    cudaLaunchAttribute at[1];
    at[0].id = cudaLaunchAttributeProgrammaticStreamSerialization;
    at[0].val.programmaticStreamSerializationAllowed = 1;
    cudaLaunchConfig_t cfg = {};
    cfg.gridDim = dim3(128); cfg.stream = cudaStreamPerThread; cfg.attrs = at; cfg.numAttrs = 1;
    cfg.blockDim = dim3(512); cfg.dynamicSmemBytes = K2_SMEM;
    cudaLaunchKernelEx(&cfg, k2_attn, wd, wo);
    cfg.blockDim = dim3(384); cfg.dynamicSmemBytes = K3_SMEM;
    cudaLaunchKernelEx(&cfg, k3_down_out, g_hs.tm_h, g_hs.tm_wd, g_hs.tm_o, g_hs.tm_wo, x, out);
}
```
